```python
import torch

def _softmax(x, axis=-1):
    return torch.softmax(x, dim=axis)
def _gelu(x):
    return torch.nn.functional.gelu(x, approximate="tanh")
def _silu(x):
    return torch.nn.functional.silu(x)
def _sigmoid(x):
    return torch.sigmoid(x)
def _layernorm(x, axis=-1, eps=1e-5):
    m = x.mean(dim=axis, keepdim=True)
    v = x.var(dim=axis, keepdim=True, unbiased=False)
    return (x - m) / torch.sqrt(v + eps)
def _scatter_add(tgt, idx, src, axis=0):
    return tgt.clone().index_add_(axis, idx, src)
def _segment_sum(src, seg, n):
    out = torch.zeros((n,) + src.shape[1:], dtype=src.dtype)
    return out.index_add_(0, seg, src)
def _pad(x, pw):
    flat = tuple(v for pair in reversed(pw) for v in pair)
    return torch.nn.functional.pad(x, flat)

kernel_name = 'sequential_preLN__gqa_block_cached__dense_activation_squared_relu__decode'

def setup_inputs():

    _w = (lambda a: (lambda t: t.to(torch.bfloat16) if t.is_floating_point() else t)(torch.as_tensor(a)))
    def _A_setup():
        B, Sq, D = 2, 1, 512
        Hq, Hkv, Sk, Dh = 32, 32, 8192, 128
        assert Hq % Hkv == 0, (Hq, Hkv)
        return {
            "x": _w((lambda *s: torch.randn(*s, dtype=torch.bfloat16) * 0.05)(B, Sq, D)),
            "k_cache": _w((lambda *s: torch.randn(*s, dtype=torch.bfloat16) * 3.2)(B, Hkv, Sk, Dh)),
            "v_cache": _w((lambda *s: torch.randn(*s, dtype=torch.bfloat16) * 0.4)(B, Hkv, Sk, Dh)),
            "wq": _w((lambda *s: torch.randn(*s, dtype=torch.bfloat16) * 3.2)(D, Hq * Dh) * (D ** -0.5)),
            "wo": _w((lambda *s: torch.randn(*s, dtype=torch.bfloat16) * 0.4)(Hq * Dh, D) * ((Hq * Dh) ** -0.5)),
        }
    _A_in = _A_setup()

    def _B_setup():
        B, S, D, F = 2, 1, 512, 1376
        return {
            "x": _w((lambda *s: torch.randn(*s, dtype=torch.bfloat16) * 0.05)(B, S, D)),
            "w1": _w((lambda *s: torch.randn(*s, dtype=torch.bfloat16) * 0.05)(D, F)),
            "b1": _w((lambda *s: torch.randn(*s, dtype=torch.bfloat16) * 0.8)(F)),
            "w2": _w((lambda *s: torch.randn(*s, dtype=torch.bfloat16) * 0.05)(F, D)),
            "b2": _w((lambda *s: torch.randn(*s, dtype=torch.bfloat16) * 3.2)(D)),
        }
    _B_in = _B_setup()

    return {
        "A_x": _A_in["x"],
        "A_k_cache": _A_in["k_cache"],
        "A_v_cache": _A_in["v_cache"],
        "A_wq": _A_in["wq"],
        "A_wo": _A_in["wo"],
        "B_x": _B_in["x"],
        "B_w1": _B_in["w1"],
        "B_b1": _B_in["b1"],
        "B_w2": _B_in["w2"],
        "B_b2": _B_in["b2"],
    }

def reference(A_x, A_k_cache, A_v_cache, A_wq, A_wo, B_x, B_w1, B_b1, B_w2, B_b2):
    def _A_ref(x, k_cache, v_cache, wq, wo):
        B, Sq, D = x.shape
        Hq, Dh = 32, 128
        Hkv = k_cache.shape[1]
        rep = Hq // Hkv
        q = (lambda x, *d: x.permute(*d))((x @ wq).reshape(B, Sq, Hq, Dh), 0, 2, 1, 3)
        k = (lambda x, n, axis: torch.repeat_interleave(x, n, dim=axis))(k_cache, rep, axis=1)
        v = (lambda x, n, axis: torch.repeat_interleave(x, n, dim=axis))(v_cache, rep, axis=1)
        scores = torch.einsum("bhqd,bhkd->bhqk", q, k) * (Dh ** -0.5)
        p = _softmax(scores, axis=-1)
        o = torch.einsum("bhqk,bhkd->bhqd", p, v)
        return (lambda x, *d: x.permute(*d))(o, 0, 2, 1, 3).reshape(B, Sq, Hq * Dh) @ wo

    def _B_ref(x, w1, b1, w2, b2):
        h = torch.einsum("bsd,df->bsf", x, w1) + b1
        zero = torch.zeros_like(h)
        r = torch.where(h > zero, h, zero)
        h = r * r
        out = torch.einsum("bsf,fd->bsd", h, w2) + b2
        return out

    x = A_x
    h = x + _A_ref(_layernorm(x, axis=-1), A_k_cache, A_v_cache, A_wq, A_wo)
    h2 = h + _B_ref(_layernorm(h, axis=-1), B_w1, B_b1, B_w2, B_b2)
    return h2
```

```cpp
#include <cuda.h>
#include <cuda_runtime.h>
#include <cuda_bf16.h>
#include <stdint.h>

namespace {

constexpr int kD = 512, kF = 1376;
constexpr int kCtas = 128;
constexpr int kTileBytes = 16384;
constexpr int kLoads = 128;
constexpr int kSlots = 13;
constexpr int kWin = 4;
constexpr int kWinMin = 3, kWinMax = 8;
constexpr int kClearAt = 32;
constexpr int kGateW1 = 124;
constexpr int kGapNs = 100;
constexpr int kThreads = 320;
constexpr int kNumA = 64;
constexpr int kB0 = 64, kNumB = 43;
constexpr int kNumC = 32;

constexpr int kOffBars = kSlots * kTileBytes;
constexpr int kOffPart = kOffBars + 512;
constexpr int kOffRed = kOffPart + 4096;
constexpr int kOffXs = kOffRed + 2048;
constexpr int kOffQs = kOffXs + 1024;
constexpr int kOffMl = kOffQs + 256;
constexpr int kOffStat = kOffMl + 64;
constexpr int kOffCs = kOffStat + 128;
constexpr int kOffHs = kOffCs + 1024;
constexpr int kSmemBytes = kOffHs + 64;
constexpr int kOffW = 6 * kTileBytes;
constexpr int kOffW2 = 8 * kTileBytes;

struct __align__(128) Scratch {
    uint32_t o1[kCtas * 64];
    uint32_t lse[kCtas * 32];
    uint32_t h2[4 * 2 * kD];
    uint32_t z3[48 * 32];
    uint32_t ready[32];
    uint32_t prog[32];
    uint32_t done[32];
};
__device__ Scratch g_s;

__device__ __forceinline__ uint32_t s2u(const void* p) { return (uint32_t)__cvta_generic_to_shared(p); }
__device__ __forceinline__ void mbar_init(uint32_t a, uint32_t c) {
    asm volatile("mbarrier.init.shared::cta.b64 [%0], %1;" ::"r"(a), "r"(c) : "memory");
}
__device__ __forceinline__ void mbar_expect(uint32_t a, uint32_t bytes) {
    asm volatile("mbarrier.arrive.expect_tx.shared::cta.b64 _, [%0], %1;" ::"r"(a), "r"(bytes) : "memory");
}
__device__ __forceinline__ void mbar_arrive(uint32_t a) {
    asm volatile("mbarrier.arrive.shared::cta.b64 _, [%0];" ::"r"(a) : "memory");
}
__device__ __forceinline__ void release_slot(uint32_t a, int lane) {
    __syncwarp();
    if (lane == 0) mbar_arrive(a);
}
__device__ __forceinline__ bool mbar_try(uint32_t a, uint32_t par) {
    uint32_t ok;
    asm volatile("{.reg .pred p; mbarrier.try_wait.parity.shared::cta.b64 p, [%1], %2; selp.u32 %0,1,0,p;}"
                 : "=r"(ok) : "r"(a), "r"(par) : "memory");
    return ok;
}
__device__ __forceinline__ bool mbar_test(uint32_t a, uint32_t par) {
    uint32_t ok;
    asm volatile("{.reg .pred p; mbarrier.test_wait.parity.shared::cta.b64 p, [%1], %2; selp.u32 %0,1,0,p;}"
                 : "=r"(ok) : "r"(a), "r"(par) : "memory");
    return ok;
}
constexpr int kMaxPolls = 1 << 22;
constexpr long long kTimeout = 4000000000LL;
__device__ __forceinline__ void mbar_wait(uint32_t a, uint32_t par) {
    if (mbar_try(a, par)) return;
    long long t0 = clock64();
    while (!mbar_try(a, par))
        if (clock64() - t0 > kTimeout) __trap();
}
__device__ __forceinline__ void bulk_load(uint32_t dst, const void* src, uint32_t bytes, uint32_t bar, uint64_t pol) {
    asm volatile(
        "cp.async.bulk.shared::cluster.global.mbarrier::complete_tx::bytes.L2::cache_hint [%0], [%1], %2, [%3], %4;"
        ::"r"(dst), "l"(src), "r"(bytes), "r"(bar), "l"(pol) : "memory");
}
__device__ __forceinline__ void tensor_load(uint32_t dst, const CUtensorMap* map, int col, int row, uint32_t bar) {
    asm volatile("cp.async.bulk.tensor.2d.shared::cluster.global.mbarrier::complete_tx::bytes [%0], [%1, {%3, %4}], [%2];"
                 ::"r"(dst), "l"(map), "r"(bar), "r"(col), "r"(row) : "memory");
}
__device__ __forceinline__ uint32_t ldg32(const void* p) {
    uint32_t v;
    asm volatile("ld.global.nc.u32 %0, [%1];" : "=r"(v) : "l"(p));
    return v;
}
__device__ __forceinline__ uint4 ldg_stream(const void* p) {
    uint4 v;
    asm volatile("ld.global.nc.L1::no_allocate.v4.u32 {%0,%1,%2,%3}, [%4];"
                 : "=r"(v.x), "=r"(v.y), "=r"(v.z), "=r"(v.w) : "l"(p));
    return v;
}
__device__ __forceinline__ uint4 ld_rlx4(const void* p) {
    uint4 v;
    asm volatile("ld.relaxed.gpu.global.v4.u32 {%0,%1,%2,%3}, [%4];"
                 : "=r"(v.x), "=r"(v.y), "=r"(v.z), "=r"(v.w) : "l"(p) : "memory");
    return v;
}
__device__ __forceinline__ uint2 ld_rlx2(const void* p) {
    uint2 v;
    asm volatile("ld.relaxed.gpu.global.v2.u32 {%0,%1}, [%2];" : "=r"(v.x), "=r"(v.y) : "l"(p) : "memory");
    return v;
}
__device__ __forceinline__ uint32_t ld_rlx1(const void* p) {
    uint32_t v;
    asm volatile("ld.relaxed.gpu.global.u32 %0, [%1];" : "=r"(v) : "l"(p) : "memory");
    return v;
}
__device__ __forceinline__ void st_rlx1(void* p, uint32_t v) {
    asm volatile("st.relaxed.gpu.global.u32 [%0], %1;" ::"l"(p), "r"(v) : "memory");
}
__device__ __forceinline__ void ldsm4(uint32_t (&r)[4], uint32_t a) {
    asm volatile("ldmatrix.sync.aligned.m8n8.x4.shared::cta.b16 {%0,%1,%2,%3}, [%4];"
                 : "=r"(r[0]), "=r"(r[1]), "=r"(r[2]), "=r"(r[3]) : "r"(a) : "memory");
}
__device__ __forceinline__ void ldsm4t(uint32_t (&r)[4], uint32_t a) {
    asm volatile("ldmatrix.sync.aligned.m8n8.x4.trans.shared::cta.b16 {%0,%1,%2,%3}, [%4];"
                 : "=r"(r[0]), "=r"(r[1]), "=r"(r[2]), "=r"(r[3]) : "r"(a) : "memory");
}
__device__ __forceinline__ void mma(float (&d)[4], const uint32_t (&a)[4], uint32_t b0, uint32_t b1) {
    asm volatile("mma.sync.aligned.m16n8k16.row.col.f32.bf16.bf16.f32 {%0,%1,%2,%3}, {%4,%5,%6,%7}, {%8,%9}, {%0,%1,%2,%3};"
                 : "+f"(d[0]), "+f"(d[1]), "+f"(d[2]), "+f"(d[3])
                 : "r"(a[0]), "r"(a[1]), "r"(a[2]), "r"(a[3]), "r"(b0), "r"(b1));
}
__device__ __forceinline__ uint32_t pack_bf16(float lo, float hi) {
    uint32_t r;
    asm("cvt.rn.bf16x2.f32 %0, %1, %2;" : "=r"(r) : "f"(hi), "f"(lo));
    return r;
}
__device__ __forceinline__ float bf_lo(uint32_t w) { return __uint_as_float(w << 16); }
__device__ __forceinline__ float bf_hi(uint32_t w) { return __uint_as_float(w & 0xffff0000u); }
__device__ __forceinline__ float rbf(float x) { return bf_lo(pack_bf16(x, 0.f)); }
__device__ __forceinline__ float ex2(float x) {
    float r;
    asm("ex2.approx.ftz.f32 %0, %1;" : "=f"(r) : "f"(x));
    return r;
}
__device__ __forceinline__ float rsqrt_fast(float x) {
    float r;
    asm("rsqrt.approx.ftz.f32 %0, %1;" : "=f"(r) : "f"(x));
    return r;
}
__device__ __forceinline__ void bar256() { asm volatile("bar.sync 1, 256;" ::: "memory"); }
__device__ __forceinline__ uint32_t nz_f32(float v) {
    uint32_t u = __float_as_uint(v);
    return u ? u : 0x80000000u;
}
__device__ __forceinline__ uint32_t nz_bf2(uint32_t u) { return u ? u : 0x80008000u; }
__device__ __forceinline__ float quad_reduce(const float (&c)[4], bool t1, bool t2) {
    float k0 = t1 ? c[2] : c[0], k1 = t1 ? c[3] : c[1];
    const float s0 = t1 ? c[0] : c[2], s1 = t1 ? c[1] : c[3];
    k0 += __shfl_xor_sync(~0u, s0, 1);
    k1 += __shfl_xor_sync(~0u, s1, 1);
    const float k = t2 ? k1 : k0, s = t2 ? k0 : k1;
    return k + __shfl_xor_sync(~0u, s, 2);
}

#define SPIN(body)                                                \
    do {                                                          \
        long long t0_ = 0;                                        \
        while (true) {                                            \
            bool ok;                                              \
            body;                                                 \
            if (__all_sync(~0u, ok)) break;                       \
            long long now_ = clock64();                           \
            if (t0_ == 0) t0_ = now_;                             \
            if (now_ - t0_ > kTimeout) __trap();                  \
        }                                                         \
    } while (0)

constexpr uint32_t kReadyMax = 2 * kCtas - 1, kProgMax = kCtas * (kLoads / 4 - 2) - 1, kDoneMax = kCtas + kNumB - 1;
__device__ __forceinline__ void red_inc(uint32_t* p, uint32_t wrap) {
    asm volatile("red.relaxed.gpu.global.inc.u32 [%0], %1;" ::"l"(p), "r"(wrap) : "memory");
}
constexpr float kLog2e = 1.4426950408889634f;

__device__ __forceinline__ uint32_t min4(const uint4& v) { return min(__vimin3_u32(v.x, v.y, v.z), v.w); }
__device__ __forceinline__ uint32_t pin(uint32_t v, int lane) { return __shfl_sync(~0u, v, lane); }
template <class T>
__device__ __forceinline__ T* pin(T* p, int lane) {
    const uint64_t v = reinterpret_cast<uint64_t>(p);
    return reinterpret_cast<T*>(((uint64_t)pin((uint32_t)(v >> 32), lane) << 32) | pin((uint32_t)v, lane));
}
__device__ __forceinline__ void sts(uint32_t a, float v) { asm volatile("st.shared.f32 [%0], %1;" ::"r"(a), "f"(v) : "memory"); }
__device__ __forceinline__ void sts(uint32_t a, uint32_t v) { asm volatile("st.shared.u32 [%0], %1;" ::"r"(a), "r"(v) : "memory"); }
__device__ __forceinline__ float lds(uint32_t a) {
    float v;
    asm volatile("ld.shared.f32 %0, [%1];" : "=f"(v) : "r"(a) : "memory");
    return v;
}
__device__ __forceinline__ float2 lds2(uint32_t a) {
    float2 v;
    asm volatile("ld.shared.v2.f32 {%0, %1}, [%2];" : "=f"(v.x), "=f"(v.y) : "r"(a) : "memory");
    return v;
}
__device__ __forceinline__ float4 lds4(uint32_t a) {
    float4 v;
    asm volatile("ld.shared.v4.f32 {%0, %1, %2, %3}, [%4];" : "=f"(v.x), "=f"(v.y), "=f"(v.z), "=f"(v.w) : "r"(a) : "memory");
    return v;
}
template <int STRIDE>
__device__ __forceinline__ float sum8(uint32_t a) {
    float v[8];
#pragma unroll
    for (int w = 0; w < 8; w++) v[w] = lds(a + w * STRIDE);
    return ((v[0] + v[1]) + (v[2] + v[3])) + ((v[4] + v[5]) + (v[6] + v[7]));
}
template <int STRIDE>
__device__ __forceinline__ float2 sum8x2(uint32_t a) {
    float2 v[8];
#pragma unroll
    for (int w = 0; w < 8; w++) v[w] = lds2(a + w * STRIDE);
    return make_float2(((v[0].x + v[1].x) + (v[2].x + v[3].x)) + ((v[4].x + v[5].x) + (v[6].x + v[7].x)),
                       ((v[0].y + v[1].y) + (v[2].y + v[3].y)) + ((v[4].y + v[5].y) + (v[6].y + v[7].y)));
}

__device__ __forceinline__ void pv16(float (&o)[4][4], uint32_t va, uint32_t p01, uint32_t p89, const uint32_t (&msk)[8]) {
    uint32_t a[8][4];
#pragma unroll
    for (int cc = 0; cc < 8; cc++) ldsm4t(a[cc], va ^ (cc << 4));
#pragma unroll
    for (int cc = 0; cc < 8; cc++) mma(o[cc & 3], a[cc], p01 & msk[cc], p89 & msk[cc]);
}
__device__ __forceinline__ void wait_count(const uint32_t* p, uint32_t n, int gap_ns) {
    const long long t0 = clock64();
    while (ld_rlx1(p) < n) {
        __nanosleep(gap_ns);
        if (clock64() - t0 > kTimeout) __trap();
    }
}

__global__ void __launch_bounds__(kThreads, 1)
fused_decode_kernel(const __grid_constant__ CUtensorMap map_wq, const __grid_constant__ CUtensorMap map_wo,
                    const __grid_constant__ CUtensorMap map_w1, const __grid_constant__ CUtensorMap map_w2,
                    const __nv_bfloat16* __restrict__ x, const __nv_bfloat16* __restrict__ kc,
                    const __nv_bfloat16* __restrict__ vc, const __nv_bfloat16* __restrict__ b1,
                    const __nv_bfloat16* __restrict__ b2, __nv_bfloat16* __restrict__ out) {
    extern __shared__ __align__(1024) unsigned char smem[];
    const uint32_t sb = s2u(smem);
    const int tid = threadIdx.x, warp = tid >> 5, lane = tid & 31;
    const int c = blockIdx.x;
    const uint32_t fullb = sb + kOffBars, emptyb = fullb + kSlots * 8;
    const uint32_t barW = emptyb + kSlots * 8, barW2 = barW + 8, barClr = barW + 64, barOk = barClr + 8;
    const int rc = ((c >> 2) & 1) * 64 + (c >> 3) * 4 + (c & 3);
    const bool roleA = rc < kNumA, roleB = rc >= kB0 && rc < kB0 + kNumB, roleC = rc >= kB0 && rc < kB0 + kNumC;

    uint64_t pol;
    asm volatile("createpolicy.fractional.L2::evict_first.b64 %0, 1.0;" : "=l"(pol));
    const char* kp = reinterpret_cast<const char*>(kc) + (size_t)c * (64 * kTileBytes);
    const char* vp = reinterpret_cast<const char*>(vc) + (size_t)c * (64 * kTileBytes);
    if (tid == 256) {
#pragma unroll
        for (int i = 0; i < kWin; i++) {
            mbar_init(fullb + (8 + i) * 8, 1);
            asm volatile("fence.mbarrier_init.release.cluster;" ::: "memory");
            mbar_expect(fullb + (8 + i) * 8, kTileBytes);
            bulk_load(sb + (8 + i) * kTileBytes, ((i & 2) ? vp : kp) + (i & 1) * kTileBytes, kTileBytes,
                      fullb + (8 + i) * 8, pol);
        }
#pragma unroll 1
        for (int j = 0; j < 8; j++) {
            mbar_init(fullb + j * 8, 1);
            asm volatile("fence.mbarrier_init.release.cluster;" ::: "memory");
            mbar_expect(fullb + j * 8, kTileBytes);
            tensor_load(sb + j * kTileBytes, &map_wq, ((c >> 1) & 31) * 128, j * 64, fullb + j * 8);
        }
    }

    if (warp == 8) {
        if (lane == 0) {
            mbar_init(fullb + 12 * 8, 1);
#pragma unroll
            for (int s = 0; s < kSlots; s++) mbar_init(emptyb + s * 8, 4);
#pragma unroll
            for (int j = 0; j < 8; j++) mbar_init(barW + j * 8, 1);
            mbar_init(barOk, 1);
            mbar_init(barClr, 1);
            asm volatile("fence.mbarrier_init.release.cluster;" ::: "memory");
        }
        __syncwarp();
        asm volatile("bar.arrive 2, 320;" ::: "memory");
        if (lane == 0) {
            static_assert(kWin == 4, "first trip issues one group");
            int slot = (8 + kWin) % kSlots, ph = (8 + kWin) / kSlots;
            int landed = 0, wslot = 8, wph = 0;
            uint32_t rank = 0;
#pragma unroll 1
            for (int grp = 1; grp < kLoads / 4; grp++) {
                int win = min(kWinMin + max(((int)rank - 48 - (grp - 2) * kCtas) >> 5, 0), kWinMax);
                if (grp <= 2) win = kWin;
                if (grp > 1 && grp < kLoads / 4 - 1)
                    asm volatile("atom.relaxed.gpu.global.inc.u32 %0, [%1], %2;"
                                 : "=r"(rank) : "l"(&g_s.prog[0]), "r"(kProgMax) : "memory");
#pragma unroll 1
                for (int i = 4 * grp; i < 4 * grp + 4; i++) {
                    while (landed <= i - win) {
                        mbar_wait(fullb + wslot * 8, wph);
                        landed++;
                        if (++wslot == kSlots) { wslot = 0; wph ^= 1; }
                    }
                    if (i >= kSlots - 8) mbar_wait(emptyb + slot * 8, ph ^ 1);
                    mbar_expect(fullb + slot * 8, kTileBytes);
                    bulk_load(sb + slot * kTileBytes, ((i & 2) ? vp : kp) + (size_t)(2 * grp + (i & 1)) * kTileBytes, kTileBytes,
                              fullb + slot * 8, pol);
                    if (i == kClearAt) mbar_arrive(barClr);
                    if (++slot == kSlots) { slot = 0; ph ^= 1; }
                }
            }
            const uint32_t lastb = fullb + ((kLoads + 7) % kSlots) * 8, lastp = ((kLoads + 7) / kSlots) & 1;
#pragma unroll 1
            for (int s = 6; s <= 10; s++) mbar_wait(emptyb + s * 8, 1);
            if (roleA) {
#pragma unroll
                for (int j = 0; j < 8; j++) mbar_expect(barW + j * 8, 8192);
                mbar_wait(lastb, lastp);
#pragma unroll
                for (int j = 0; j < 8; j++)
                    tensor_load(sb + kOffW + j * 8192, &map_wo, (rc & 15) * 32, (rc >> 4) * 1024 + j * 128, barW + j * 8);
            } else if (roleB) {
                mbar_expect(barW, 2 * kTileBytes);
                if (roleC) mbar_expect(barW2, 3 * kTileBytes);
                wait_count(&g_s.done[0], kGateW1, kGapNs);
                mbar_wait(lastb, lastp);
#pragma unroll
                for (int j = 0; j < 2; j++) tensor_load(sb + kOffW + j * kTileBytes, &map_w1, (rc - kB0) * 32, j * 256, barW);
                wait_count(&g_s.done[0], kCtas, kGapNs);
                if (roleC) {
#pragma unroll
                    for (int j = 0; j < 6; j++) tensor_load(sb + kOffW2 + j * 8192, &map_w2, (rc - kB0) * 16, j * 256, barW2);
                }
                red_inc(&g_s.done[0], kDoneMax);
            }
        }
    } else if (warp == 9) {
        if (lane == 0) {
            asm volatile("prefetch.tensormap [%0];" ::"l"(roleA ? &map_wo : &map_w1) : "memory");
            asm volatile("prefetch.tensormap [%0];" ::"l"(&map_w2) : "memory");
            red_inc(&g_s.prog[0], kProgMax);
        }
        __syncwarp();
        asm volatile("bar.sync 2, 320;" ::: "memory");
        mbar_wait(barClr, 0);
        st_rlx1(&g_s.o1[c * 64 + lane], 0);
        st_rlx1(&g_s.o1[c * 64 + 32 + lane], 0);
        if (roleA) {
            st_rlx1(&g_s.h2[(rc >> 4) * 1024 + (rc & 15) * 32 + lane], 0);
            st_rlx1(&g_s.h2[(rc >> 4) * 1024 + kD + (rc & 15) * 32 + lane], 0);
        }
        if (roleB) st_rlx1(&g_s.z3[(rc - kB0) * 32 + lane], 0);
        if (lane < 8) st_rlx1(&g_s.lse[c * 32 + lane], 0);
        __syncwarp();
        __threadfence();
        if (lane == 0) red_inc(&g_s.ready[0], kReadyMax);
        SPIN({
            ok = ld_rlx1(&g_s.ready[0]) >= kCtas;
            if (!ok) __nanosleep(500);
        });
        __threadfence();
        if (lane == 0) {
            mbar_arrive(barOk);
            red_inc(&g_s.ready[0], kReadyMax);
        }
        if (roleB) {
            const int cb = rc - kB0;
            const uint32_t bias2 = ldg32(b1 + cb * 32 + 2 * (lane & 15));
            const uint32_t a_rr = pin(sb + kOffRed + lane * 8, lane);
            const uint32_t a_sr = pin(sb + kOffStat + (lane >> 4) * 64, lane);
            uint32_t* const g_z = pin(&g_s.z3[cb * 32 + (lane & 24) + (lane & 3) * 2 + ((lane >> 2) & 1)], lane);
#pragma unroll 1
            for (int pass = 0; pass < 2; pass++) {
                if (pass) asm volatile("bar.sync 3, 288;" ::: "memory");
                const float2 csum = sum8x2<128>(sb + kOffCs + (lane & 15) * 8);
                if (pass) asm volatile("bar.sync 4, 288;" ::: "memory");
                const float4 q0 = lds4(a_sr), q1 = lds4(a_sr + 16), q2 = lds4(a_sr + 32), q3 = lds4(a_sr + 48);
                const float mu = (((q0.x + q0.y) + (q0.z + q0.w)) + ((q1.x + q1.y) + (q1.z + q1.w))) * (1.f / kD);
                const float sq2 = ((q2.x + q2.y) + (q2.z + q2.w)) + ((q3.x + q3.y) + (q3.z + q3.w));
                const float ve = rbf(rbf(fmaxf(sq2 * (1.f / kD) - mu * mu, 0.f)) + 1e-5f), rq = rsqrt_fast(ve);
                const float inv = rq * (2.f - rbf(ve * rq) * rq);
                const float mb = rbf(mu);
                const float c0 = -mb * csum.x * inv, c1 = -mb * csum.y * inv;
                if (pass) asm volatile("bar.sync 5, 288;" ::: "memory");
                const float2 p = sum8x2<256>(a_rr);
                const uint32_t ub = pack_bf16(p.x * inv + c0, p.y * inv + c1);
                const uint32_t uc = pack_bf16(bf_lo(ub) + bf_lo(bias2), bf_hi(ub) + bf_hi(bias2));
                const float r0 = fmaxf(bf_lo(uc), 0.f), r1 = fmaxf(bf_hi(uc), 0.f);
                const uint32_t z = nz_bf2(pack_bf16(r0 * r0, r1 * r1));
                if (pass) st_rlx1(g_z, z);
            }
        }
    } else {
        const int g = lane >> 2, t = lane & 3;
        const int bb = g & 1, sc = g >> 1;
        const int gi = warp >> 2, wq4 = warp & 3;
        const int mi = lane >> 3, r = lane & 7;
        float* part = reinterpret_cast<float*>(smem + kOffPart);
        uint32_t* xs = reinterpret_cast<uint32_t*>(smem + kOffXs);
        uint32_t* qs = reinterpret_cast<uint32_t*>(smem + kOffQs);
        float* ml = reinterpret_cast<float*>(smem + kOffMl);

        uint32_t xt0, xt1;
        float bias = 0.f;
        {
            const __nv_bfloat16* xrow = x + (c >> 6) * kD;
            const uint4 xa = ldg_stream(xrow + lane * 16), xb = ldg_stream(xrow + lane * 16 + 8);
            const uint32_t xo = ldg32(xrow + tid * 2);
            xt0 = ldg32(x + bb * kD + 64 * warp + 16 * sc + 2 * t);
            xt1 = ldg32(x + bb * kD + 64 * warp + 16 * sc + 8 + 2 * t);
            if (roleC) bias = __bfloat162float(b2[(rc - kB0) * 16 + (lane & 15)]);
            const uint32_t xw[8] = {xa.x, xa.y, xa.z, xa.w, xb.x, xb.y, xb.z, xb.w};
            float s = 0.f;
#pragma unroll
            for (int i = 0; i < 8; i++) s += bf_lo(xw[i]) + bf_hi(xw[i]);
#pragma unroll
            for (int o = 16; o; o >>= 1) s += __shfl_xor_sync(~0u, s, o);
            const float mean = s * (1.f / kD);
            float q2 = 0.f;
#pragma unroll
            for (int i = 0; i < 8; i++)
                q2 += (bf_lo(xw[i]) - mean) * (bf_lo(xw[i]) - mean) + (bf_hi(xw[i]) - mean) * (bf_hi(xw[i]) - mean);
#pragma unroll
            for (int o = 16; o; o >>= 1) q2 += __shfl_xor_sync(~0u, q2, o);
            const float mb = rbf(mean);
            const float den = rbf(__fsqrt_rn(rbf(rbf(q2 * (1.f / kD)) + 1e-5f)));
            xs[tid] = pack_bf16(__fdiv_rn(rbf(bf_lo(xo) - mb), den), __fdiv_rn(rbf(bf_hi(xo) - mb), den));
        }
        asm volatile("bar.sync 2, 320;" ::: "memory");

        uint32_t msk[8];
#pragma unroll
        for (int cc = 0; cc < 8; cc++)
            msk[cc] = (cc == (g ^ (2 * t)) ? 0x0000ffffu : 0u) | (cc == (g ^ (2 * t + 1)) ? 0xffff0000u : 0u);
        const uint32_t koff = wq4 * 4096 + (r + 8 * (mi & 1)) * 256 + (mi >> 1) * 128 + r * 16;
        const uint32_t voff = wq4 * 4096 + (r + 8 * (mi >> 1)) * 256 + (mi & 1) * 128 + r * 16;
        float* pw = part + warp * 128 + 16 * t + g;

        uint32_t qf[16];
        float o[4][4] = {};
        {
#pragma unroll 1
            for (int j = gi; j < 8; j += 2) {
                const uint32_t p01 = xs[32 * j + 8 * wq4 + t], p89 = xs[32 * j + 8 * wq4 + 4 + t];
                mbar_wait(fullb + j * 8, 0);
                pv16(o, sb + j * kTileBytes + voff, p01, p89, msk);
                release_slot(emptyb + j * 8, lane);
            }
            pw[0] = (o[0][0] + o[1][0]) + (o[2][0] + o[3][0]);
            pw[8] = (o[0][1] + o[1][1]) + (o[2][1] + o[3][1]);
            pw[64] = (o[0][2] + o[1][2]) + (o[2][2] + o[3][2]);
            pw[72] = (o[0][3] + o[1][3]) + (o[2][3] + o[3][3]);
            bar256();
            if (tid < 64) {
                float a0 = 0.f, a1 = 0.f;
#pragma unroll
                for (int w = 0; w < 8; w++) {
                    const float2 p = *reinterpret_cast<const float2*>(part + w * 128 + tid * 2);
                    a0 += p.x;
                    a1 += p.y;
                }
                qs[tid] = pack_bf16(a0, a1);
            }
            bar256();
#pragma unroll
            for (int cc = 0; cc < 8; cc++) {
                qf[2 * cc] = qs[(cc ^ g) * 4 + t];
                qf[2 * cc + 1] = qs[32 + (cc ^ g) * 4 + t];
            }
#pragma unroll
            for (int k = 0; k < 16; k++) o[k >> 2][k & 3] = 0.f;
        }

        float mrun = -INFINITY, lrun = 0.f, oscale = 0.f;
        const bool diag = (t == (g >> 1));
        const bool odd = g & 1;
        int slot = 8 + gi, ph = 0;
        const uint32_t a_pw = pin(sb + kOffPart + (warp * 128 + 16 * t + g) * 4, lane);
        const uint32_t a_pr = pin(sb + kOffPart + (tid & 63) * 8, lane);
        uint32_t* const g_o = pin(&g_s.o1[c * 64 + (tid & 48) + (tid & 3) * 4 + ((tid >> 2) & 3)], lane);
        const int wid = pin(warp, lane);
#pragma unroll 1
        for (int it = 0; it < 32; it++) {
            int vslot = slot + 2, vph = ph;
            if (vslot >= kSlots) { vslot -= kSlots; vph ^= 1; }
            mbar_wait(fullb + slot * 8, ph);
            const uint32_t ka = sb + slot * kTileBytes + koff;
            float s0[4] = {0.f, 0.f, 0.f, 0.f}, s1[4] = {0.f, 0.f, 0.f, 0.f};
#pragma unroll
            for (int cc = 0; cc < 8; cc += 2) {
                uint32_t a[4], a2[4];
                ldsm4(a, ka ^ (cc << 4));
                ldsm4(a2, ka ^ ((cc + 1) << 4));
                mma(s0, a, qf[2 * cc], qf[2 * cc + 1]);
                mma(s1, a2, qf[2 * cc + 2], qf[2 * cc + 3]);
            }
            release_slot(emptyb + slot * 8, lane);
            const float dlo = odd ? s0[1] + s1[1] : s0[0] + s1[0];
            const float dhi = odd ? s0[3] + s1[3] : s0[2] + s1[2];
            uint32_t pk = pack_bf16(dlo, dhi);
            pk = pack_bf16(bf_lo(pk) * 0.08838834764831845f, bf_hi(pk) * 0.08838834764831845f);
            const float slo = bf_lo(pk), shi = bf_hi(pk);
            int key = __float_as_int(fmaxf(slo, shi));
            key ^= (key >> 31) & 0x7fffffff;
            key = __reduce_max_sync(~0u, diag ? key : (int)0x80000000);
            key ^= (key >> 31) & 0x7fffffff;
            const float ms = fmaxf(mrun, __int_as_float(key) * kLog2e);
            const float alpha = ex2(mrun - ms);
            const float plo = ex2(slo * kLog2e - ms), phi = ex2(shi * kLog2e - ms);
            mrun = ms;
            lrun = lrun * alpha + (diag ? plo + phi : 0.f);
            const uint32_t pp = pack_bf16(plo, phi);
            const uint32_t pa = __shfl_sync(~0u, pp, 9 * t), pb = __shfl_sync(~0u, pp, 9 * t + 4);
            const uint32_t p01 = __byte_perm(pa, pb, 0x5410), p89 = __byte_perm(pa, pb, 0x7632);
#pragma unroll
            for (int k = 0; k < 16; k++) o[k >> 2][k & 3] *= alpha;
            if (it == 31) {
                float lw = lrun;
#pragma unroll
                for (int of = 16; of; of >>= 1) lw += __shfl_xor_sync(~0u, lw, of);
                if (lane == 0) *reinterpret_cast<float2*>(ml + warp * 2) = make_float2(mrun, lw);
                mbar_wait(barOk, 0);
                bar256();
                float mw[8], lv[8];
#pragma unroll
                for (int w = 0; w < 8; w += 2) {
                    const float4 q = *reinterpret_cast<const float4*>(ml + w * 2);
                    mw[w] = q.x; lv[w] = q.y; mw[w + 1] = q.z; lv[w + 1] = q.w;
                }
                const float m = fmaxf(fmaxf(fmaxf(mw[0], mw[1]), fmaxf(mw[2], mw[3])),
                                      fmaxf(fmaxf(mw[4], mw[5]), fmaxf(mw[6], mw[7])));
                float l = 0.f;
#pragma unroll
                for (int w = 0; w < 8; w++) l += ex2(mw[w] - m) * lv[w];
                oscale = __fdividef(ex2(ms - m), l);
                if (tid < 8) st_rlx1(&g_s.lse[c * 32 + tid], nz_f32(m + __log2f(l)));
                if (tid == 32) red_inc(&g_s.done[0], kDoneMax);
            }
            mbar_wait(fullb + vslot * 8, vph);
            pv16(o, sb + vslot * kTileBytes + voff, p01, p89, msk);
            release_slot(emptyb + vslot * 8, lane);
            slot += 4;
            if (slot >= kSlots) { slot -= kSlots; ph ^= 1; }
        }

        sts(a_pw, ((o[0][0] + o[1][0]) + (o[2][0] + o[3][0])) * oscale);
        sts(a_pw + 32, ((o[0][1] + o[1][1]) + (o[2][1] + o[3][1])) * oscale);
        sts(a_pw + 256, ((o[0][2] + o[1][2]) + (o[2][2] + o[3][2])) * oscale);
        sts(a_pw + 288, ((o[0][3] + o[1][3]) + (o[2][3] + o[3][3])) * oscale);
        bar256();
        if (wid < 2) {
            const float2 p = sum8x2<512>(a_pr);
            st_rlx1(g_o, nz_bf2(pack_bf16(p.x, p.y)));
        }

        if (roleA) {
            const int ks = rc >> 4, ns = rc & 15;
            const int c0 = (bb * 32 + ks * 8 + warp) * 2;
            const uint32_t* p0 = &g_s.o1[c0 * 64 + (sc * 4 + t) * 4];
            uint32_t l0 = ld_rlx1(&g_s.lse[c0 * 32]), l1 = ld_rlx1(&g_s.lse[c0 * 32 + 32]);
            uint4 u0 = ld_rlx4(p0), u1 = ld_rlx4(p0 + 64);
            const uint32_t wa = pin(sb + kOffW + warp * 8192 + (8 * (mi >> 1) + r) * 64 + (((mi & 1) ^ (r >> 1)) << 4), lane);
            const uint32_t a_rw = pin(sb + kOffRed + (warp * 64 + (t >> 1) * 32 + g + 8 * (t & 1)) * 4, lane);
            const uint32_t a_rr = pin(sb + kOffRed + (tid & 63) * 4, lane);
            uint32_t* const g_h = pin(&g_s.h2[ks * 1024 + (warp & 1) * kD + ns * 32 + (lane & 16) + ((lane >> 1) & 3) * 4 +
                                              ((lane >> 3) & 1) * 2 + (lane & 1)], lane);
            const int tq = pin(t, lane), sq = pin(sc, lane);
            const bool t1 = tq & 1, t2 = tq & 2;
            SPIN({
                ok = l0 && l1;
                if (!__all_sync(~0u, ok)) {
                    __nanosleep(kGapNs);
                    l0 = ld_rlx1(&g_s.lse[c0 * 32]);
                    l1 = ld_rlx1(&g_s.lse[c0 * 32 + 32]);
                }
            });
            const float dl = __uint_as_float(l1) - __uint_as_float(l0);
            const float a0 = __fdividef(1.f, 1.f + ex2(dl)), a1 = __fdividef(1.f, 1.f + ex2(-dl));
            uint32_t af[8][2][4];
            const uint32_t barWw = barW + wid * 8;
            const bool early = __all_sync(~0u, mbar_test(barWw, 0));
            if (early) {
#pragma unroll
                for (int j = 0; j < 16; j++) ldsm4t(af[j >> 1][j & 1], (wa ^ ((j & 1) * 32)) + (j >> 1) * 1024);
            }
            for (int n = 0;; n++) {
                const bool e0 = min4(u0) == 0, e1 = min4(u1) == 0;
                if (!__any_sync(~0u, e0 || e1)) break;
                if (e0) u0 = ld_rlx4(p0);
                if (e1) u1 = ld_rlx4(p0 + 64);
                if (n > kMaxPolls) __trap();
            }
            uint32_t R[4];
            R[0] = pack_bf16(a0 * bf_lo(u0.x) + a1 * bf_lo(u1.x), a0 * bf_hi(u0.x) + a1 * bf_hi(u1.x));
            R[1] = pack_bf16(a0 * bf_lo(u0.y) + a1 * bf_lo(u1.y), a0 * bf_hi(u0.y) + a1 * bf_hi(u1.y));
            R[2] = pack_bf16(a0 * bf_lo(u0.z) + a1 * bf_lo(u1.z), a0 * bf_hi(u0.z) + a1 * bf_hi(u1.z));
            R[3] = pack_bf16(a0 * bf_lo(u0.w) + a1 * bf_lo(u1.w), a0 * bf_hi(u0.w) + a1 * bf_hi(u1.w));
            uint32_t bf[8][2];
#pragma unroll
            for (int j = 0; j < 8; j++) {
                bf[j][0] = sq == (j >> 1) ? R[2 * (j & 1)] : 0u;
                bf[j][1] = sq == (j >> 1) ? R[2 * (j & 1) + 1] : 0u;
            }
            float d[2][2][4] = {};
            if (early) {
#pragma unroll
                for (int j = 0; j < 16; j++) mma(d[j & 1][(j >> 1) & 1], af[j >> 1][j & 1], bf[j >> 1][0], bf[j >> 1][1]);
            } else {
                mbar_wait(barWw, 0);
#pragma unroll
                for (int j = 0; j < 20; j++) {
                    if (j < 16) ldsm4t(af[j >> 1][j & 1], (wa ^ ((j & 1) * 32)) + (j >> 1) * 1024);
                    if (j >= 4) {
                        const int m = j - 4;
                        mma(d[m & 1][(m >> 1) & 1], af[m >> 1][m & 1], bf[m >> 1][0], bf[m >> 1][1]);
                    }
                }
            }
#pragma unroll
            for (int mt = 0; mt < 2; mt++) {
                float e[4];
#pragma unroll
                for (int k = 0; k < 4; k++) e[k] = d[mt][0][k] + d[mt][1][k];
                sts(a_rw + mt * 64, quad_reduce(e, t1, t2));
            }
            bar256();
            if (wid < 2) st_rlx1(g_h, nz_f32(sum8<256>(a_rr)));
        } else if (roleB) {
            const int cb = rc - kB0;
            const uint32_t wa = sb + kOffW + warp * 4096 + (8 * (mi >> 1) + r) * 64 + (((mi & 1) ^ (r >> 1)) << 4);
            const uint32_t a_rw = pin(sb + kOffRed + (warp * 64 + (t >> 1) * 32 + g + 8 * (t & 1)) * 4, lane);
            const uint32_t a_sw = pin(sb + kOffStat + ((t >> 1) * 16 + (t & 1) * 8 + warp) * 4, lane);
            const uint32_t a_hw = pin(sb + kOffHs + (bb * 8 + t) * 4, lane);
            const uint32_t* const hp = pin(&g_s.h2[bb * kD + 64 * warp + 16 * sc + 4 * t], lane);
            const int tq = pin(t, lane), sq = pin(sc, lane);
            const bool t1 = tq & 1, t2 = tq & 2;
            const bool wr_stat = pin(g == 0, lane), wr_h = pin(roleC && warp * 4 + sc == cb, lane);
            mbar_wait(barW, 0);
            uint32_t af[4][2][4];
#pragma unroll
            for (int j = 0; j < 8; j++) ldsm4t(af[j >> 1][j & 1], (wa ^ ((j & 1) * 32)) + (j >> 1) * 1024);
            {
                const uint32_t one = g == 0 ? 0x3f803f80u : 0u;
#pragma unroll
                for (int mt = 0; mt < 2; mt++) {
                    float d[4] = {0.f, 0.f, 0.f, 0.f};
#pragma unroll
                    for (int j = 0; j < 4; j++) mma(d, af[j][mt], one, one);
                    if (t == 0) {
                        sts(sb + kOffCs + (warp * 32 + mt * 16 + g) * 4, d[0]);
                        sts(sb + kOffCs + (warp * 32 + mt * 16 + g + 8) * 4, d[2]);
                    }
                }
            }
            asm volatile("bar.arrive 3, 288;" ::: "memory");
            uint4 y0 = ld_rlx4(hp), y1 = ld_rlx4(hp + 1024), y2 = ld_rlx4(hp + 2048), y3 = ld_rlx4(hp + 3072);
            for (int n = 0;; n++) {
                const bool e0 = min4(y0) == 0, e1 = min4(y1) == 0, e2 = min4(y2) == 0, e3 = min4(y3) == 0;
                if (!__any_sync(~0u, e0 || e1 || e2 || e3)) break;
                if (e0) y0 = ld_rlx4(hp);
                if (e1) y1 = ld_rlx4(hp + 1024);
                if (e2) y2 = ld_rlx4(hp + 2048);
                if (e3) y3 = ld_rlx4(hp + 3072);
                if (n > kMaxPolls) __trap();
            }
#define SUM4(f) ((__uint_as_float(y0.f) + __uint_as_float(y1.f)) + (__uint_as_float(y2.f) + __uint_as_float(y3.f)))
            const uint32_t at0 = pack_bf16(SUM4(x), SUM4(y)), at1 = pack_bf16(SUM4(z), SUM4(w));
#undef SUM4
            const uint32_t h0 = pack_bf16(bf_lo(xt0) + bf_lo(at0), bf_hi(xt0) + bf_hi(at0));
            const uint32_t h1 = pack_bf16(bf_lo(xt1) + bf_lo(at1), bf_hi(xt1) + bf_hi(at1));
            {
                const float v0 = bf_lo(h0), v1 = bf_hi(h0), v2 = bf_lo(h1), v3 = bf_hi(h1);
                const float q = (v0 * v0 + v1 * v1) + (v2 * v2 + v3 * v3), sm = (v0 + v1) + (v2 + v3);
                const uint32_t hi = pack_bf16(sm, q);
                const uint32_t lo = pack_bf16(sm - bf_lo(hi), q - bf_hi(hi));
                const uint32_t sel[4] = {0x3f803f80u, 0u, 0u, 0x3f803f80u};
                float ds[4] = {0.f, 0.f, 0.f, 0.f};
                mma(ds, sel, __byte_perm(hi, lo, 0x5410), __byte_perm(hi, lo, 0x7632));
                const float v = quad_reduce(ds, t1, t2);
                if (wr_stat) sts(a_sw, v);
                asm volatile("bar.arrive 4, 288;" ::: "memory");
            }
            float d[2][2][4] = {};
#pragma unroll
            for (int j = 0; j < 4; j++) {
                const uint32_t b0 = sq == j ? h0 : 0u, b1v = sq == j ? h1 : 0u;
                mma(d[0][j & 1], af[j][0], b0, b1v);
                mma(d[1][j & 1], af[j][1], b0, b1v);
            }
            if (wr_h) {
                sts(a_hw, h0);
                sts(a_hw + 16, h1);
            }
#pragma unroll
            for (int mt = 0; mt < 2; mt++) {
                float e[4];
#pragma unroll
                for (int k = 0; k < 4; k++) e[k] = d[mt][0][k] + d[mt][1][k];
                sts(a_rw + mt * 64, quad_reduce(e, t1, t2));
            }
            asm volatile("bar.arrive 5, 288;" ::: "memory");
            if (roleC) {
                mbar_wait(barW2, 0);
                const uint32_t w2a = sb + kOffW2 + warp * 6144 + (8 * (mi >> 1) + r) * 32 + (((mi & 1) ^ (r >> 2)) << 4);
                uint32_t a2[12][4];
#pragma unroll
                for (int j = 0; j < 12; j++) ldsm4t(a2[j], w2a + j * 512);
                const uint32_t a_hr = pin(sb + kOffHs + (lane >> 1) * 4, lane), hsh = pin((lane & 1) * 16, lane);
                const uint32_t a_cw = pin(sb + kOffPart + (warp * 32 + (t >> 1) * 16 + g + 8 * (t & 1)) * 4, lane);
                const uint32_t a_cr = pin(sb + kOffPart + lane * 4, lane);
                __nv_bfloat16* const g_out = pin(out + (lane >> 4) * kD + cb * 16 + (lane & 15), lane);
                const uint32_t* const zp = pin(&g_s.z3[(6 * warp + (sc >> 1)) * 32 + bb * 16 + (sc & 1) * 8 + 2 * t], lane);
                const int f0 = 192 * warp + 16 * sc;
                const bool v0 = f0 < kF, v1 = f0 + 64 < kF;
                uint2 z0 = make_uint2(0x80008000u, 0x80008000u), z1 = z0, z2 = z0;
                if (v0) z0 = ld_rlx2(zp);
                if (v1) z1 = ld_rlx2(zp + 64);
                if (v1) z2 = ld_rlx2(zp + 128);
                for (int n = 0;; n++) {
                    const bool e0 = min(z0.x, z0.y) == 0, e1 = min(z1.x, z1.y) == 0, e2 = min(z2.x, z2.y) == 0;
                    if (!__any_sync(~0u, e0 || e1 || e2)) break;
                    if (e0) z0 = ld_rlx2(zp);
                    if (e1) z1 = ld_rlx2(zp + 64);
                    if (e2) z2 = ld_rlx2(zp + 128);
                    if (n > kMaxPolls) __trap();
                }
                float d2[4][4] = {};
#pragma unroll
                for (int j = 0; j < 4; j++) mma(d2[j], a2[j], sq == j ? z0.x : 0u, sq == j ? z0.y : 0u);
#pragma unroll
                for (int j = 0; j < 4; j++) mma(d2[j], a2[4 + j], sq == j ? z1.x : 0u, sq == j ? z1.y : 0u);
#pragma unroll
                for (int j = 0; j < 4; j++) mma(d2[j], a2[8 + j], sq == j ? z2.x : 0u, sq == j ? z2.y : 0u);
                float e[4];
#pragma unroll
                for (int k = 0; k < 4; k++) e[k] = (d2[0][k] + d2[1][k]) + (d2[2][k] + d2[3][k]);
                sts(a_cw, quad_reduce(e, t1, t2));
                bar256();
                if (wid == 0) {
                    const float hres = __uint_as_float((__float_as_uint(lds(a_hr)) >> hsh) << 16);
                    *g_out = __float2bfloat16(hres + rbf(rbf(sum8<128>(a_cr)) + bias));
                }
            }
        }
    }
}

using EncodeFn = CUresult (*)(CUtensorMap*, CUtensorMapDataType, cuuint32_t, void*, const cuuint64_t*, const cuuint64_t*,
                              const cuuint32_t*, const cuuint32_t*, CUtensorMapInterleave, CUtensorMapSwizzle,
                              CUtensorMapL2promotion, CUtensorMapFloatOOBfill);

void encode2d(EncodeFn fn, CUtensorMap* m, void* base, uint64_t rows, uint64_t cols, uint32_t box_rows, uint32_t box_cols,
              CUtensorMapSwizzle sw, CUtensorMapL2promotion promo) {
    const cuuint64_t dims[2] = {cols, rows};
    const cuuint64_t strides[1] = {cols * 2};
    const cuuint32_t box[2] = {box_cols, box_rows};
    const cuuint32_t es[2] = {1, 1};
    fn(m, CU_TENSOR_MAP_DATA_TYPE_BFLOAT16, 2, base, dims, strides, box, es, CU_TENSOR_MAP_INTERLEAVE_NONE, sw,
       promo, CU_TENSOR_MAP_FLOAT_OOB_FILL_NONE);
}

}

extern "C" void kernel_launch(void* const* d_in, const int* in_sizes, int n_in, void* d_out, int out_size) {
    (void)in_sizes; (void)n_in; (void)out_size;
    static EncodeFn encode = nullptr;
    if (!encode) {
        void* fn = nullptr;
        cudaDriverEntryPointQueryResult qr;
        cudaGetDriverEntryPoint("cuTensorMapEncodeTiled", &fn, cudaEnableDefault, &qr);
        encode = reinterpret_cast<EncodeFn>(fn);
        cudaFuncSetAttribute(fused_decode_kernel, cudaFuncAttributeMaxDynamicSharedMemorySize, kSmemBytes);
    }
    CUtensorMap mq, mo, m1, m2;
    encode2d(encode, &mq, d_in[3], kD, 4096, 64, 128, CU_TENSOR_MAP_SWIZZLE_NONE, CU_TENSOR_MAP_L2_PROMOTION_NONE);
    encode2d(encode, &mo, d_in[4], 4096, kD, 128, 32, CU_TENSOR_MAP_SWIZZLE_64B, CU_TENSOR_MAP_L2_PROMOTION_L2_256B);
    encode2d(encode, &m1, d_in[6], kD, kF, 256, 32, CU_TENSOR_MAP_SWIZZLE_64B, CU_TENSOR_MAP_L2_PROMOTION_L2_256B);
    encode2d(encode, &m2, d_in[8], kF, kD, 256, 16, CU_TENSOR_MAP_SWIZZLE_32B, CU_TENSOR_MAP_L2_PROMOTION_L2_256B);
    using bf = __nv_bfloat16;
    fused_decode_kernel<<<kCtas, kThreads, kSmemBytes>>>(mq, mo, m1, m2, (const bf*)d_in[0], (const bf*)d_in[1],
                                                         (const bf*)d_in[2], (const bf*)d_in[7], (const bf*)d_in[9],
                                                         (bf*)d_out);
}
```
